```python
import torch

def _softmax(x, axis=-1):
    return torch.softmax(x, dim=axis)
def _gelu(x):
    return torch.nn.functional.gelu(x, approximate="tanh")
def _silu(x):
    return torch.nn.functional.silu(x)
def _sigmoid(x):
    return torch.sigmoid(x)
def _layernorm(x, axis=-1, eps=1e-5):
    m = x.mean(dim=axis, keepdim=True)
    v = x.var(dim=axis, keepdim=True, unbiased=False)
    return (x - m) / torch.sqrt(v + eps)
def _scatter_add(tgt, idx, src, axis=0):
    return tgt.clone().index_add_(axis, idx, src)
def _segment_sum(src, seg, n):
    out = torch.zeros((n,) + src.shape[1:], dtype=src.dtype)
    return out.index_add_(0, seg, src)
def _pad(x, pw):
    flat = tuple(v for pair in reversed(pw) for v in pair)
    return torch.nn.functional.pad(x, flat)

kernel_name = 'gated_mix__ssm_conv_s4__linear_kernel_hedgehog__prompt'

def setup_inputs():

    _w = (lambda a: (lambda t: t.to(torch.bfloat16) if t.is_floating_point() else t)(torch.as_tensor(a)))
    def _A_setup():
        B, L, D, N = 1, 2048, 1024, 128
        A_re = -(lambda _x: torch.exp(torch.as_tensor(_x)))((lambda *s: torch.randn(*s, dtype=torch.bfloat16) * 6.4)(D, N))
        A_im = torch.pi * (lambda *s: torch.randn(*s, dtype=torch.bfloat16) * 0.1)(D, N)
        B_re = (lambda *s: torch.randn(*s, dtype=torch.bfloat16) * 0.2)(D, N)
        B_im = (lambda *s: torch.randn(*s, dtype=torch.bfloat16) * 0.2)(D, N)
        C_re = (lambda *s: torch.randn(*s, dtype=torch.bfloat16) * 0.2)(D, N)
        C_im = (lambda *s: torch.randn(*s, dtype=torch.bfloat16) * 0.2)(D, N)
        log_dt = (lambda *s: torch.randn(*s, dtype=torch.bfloat16) * 0.1)(D) * 0.5 - 4.0
        Dskip = (lambda *s: torch.randn(*s, dtype=torch.bfloat16) * 0.1)(D)
        return {
            "u": _w((lambda *s: torch.randn(*s, dtype=torch.bfloat16) * 0.05)(B, L, D)),
            "A_re": _w(A_re),
            "A_im": _w(A_im),
            "B_re": _w(B_re),
            "B_im": _w(B_im),
            "C_re": _w(C_re),
            "C_im": _w(C_im),
            "log_dt": _w(log_dt),
            "Dskip": _w(Dskip),
        }
    _A_in = _A_setup()

    def _B_setup():
        B, S, D, H = 1, 2048, 1024, 32
        Dh = D // H
        return {
            "x": _w((lambda *s: torch.randn(*s, dtype=torch.bfloat16) * 0.05)(B, S, D)),
            "wqkv": _w((lambda *s: torch.randn(*s, dtype=torch.bfloat16) * 0.8)(D, 3 * D)),
            "w_phi": _w((lambda *s: torch.randn(*s, dtype=torch.bfloat16) * 0.8)(H, Dh, Dh) * (Dh ** -0.5)),
            "wo": _w((lambda *s: torch.randn(*s, dtype=torch.bfloat16) * 0.05)(D, D)),
        }
    _B_in = _B_setup()

    return {
        "A_u": _A_in["u"],
        "A_A_re": _A_in["A_re"],
        "A_A_im": _A_in["A_im"],
        "A_B_re": _A_in["B_re"],
        "A_B_im": _A_in["B_im"],
        "A_C_re": _A_in["C_re"],
        "A_C_im": _A_in["C_im"],
        "A_log_dt": _A_in["log_dt"],
        "A_Dskip": _A_in["Dskip"],
        "B_x": _B_in["x"],
        "B_wqkv": _B_in["wqkv"],
        "B_w_phi": _B_in["w_phi"],
        "B_wo": _B_in["wo"],
        "gate_w": _w((lambda *s: torch.randn(*s, dtype=torch.bfloat16) * 0.05)(1024) * 16.0),
    }

def reference(A_u, A_A_re, A_A_im, A_B_re, A_B_im, A_C_re, A_C_im, A_log_dt, A_Dskip, B_x, B_wqkv, B_w_phi, B_wo, gate_w):
    def _A_ref(u, A_re, A_im, B_re, B_im, C_re, C_im, log_dt, Dskip):
        Bsz, L, D = u.shape
        dt = torch.exp(log_dt)[:, None]
        A = A_re + 1j * A_im
        Bc = B_re + 1j * B_im
        Cc = C_re + 1j * C_im
        logdA = dt * A
        dB = dt * Bc
        l = (lambda x, dt: x.to(dt))(torch.arange(L), A_re.dtype)
        P = torch.exp(logdA[:, :, None] * l[None, None, :])
        K = torch.einsum("dn,dnl,dn->dl", Cc, P, dB).real
        L2 = 2 * L
        Kp = _pad(K, ((0, 0), (0, L)))
        up = (lambda x, *d: x.permute(*d))(u, 0, 2, 1)
        up = _pad(up, ((0, 0), (0, 0), (0, L)))
        Kf = (lambda x, axes=(-2,-1): torch.fft.rfft2(x.float(), dim=axes))(Kp[:, None, :], axes=(-2, -1))
        Uf = (lambda x, axes=(-2,-1): torch.fft.rfft2(x.float(), dim=axes))(up[:, :, None, :], axes=(-2, -1))
        Yf = Uf * Kf[None, :, :, :]
        y = (lambda x, s, axes=(-2,-1): torch.fft.irfft2(x, s=s, dim=axes).to(torch.bfloat16))(Yf, (1, L2), axes=(-2, -1))[:, :, 0, :L]
        y = (lambda x, *d: x.permute(*d))(y, 0, 2, 1) + u * Dskip[None, None, :]
        return y

    def _B_ref(x, wqkv, w_phi, wo):
        B, S, D = x.shape
        H = 32; Dh = D // H
        qkv = (lambda x, *d: x.permute(*d))((x @ wqkv).reshape(B, S, 3, H, Dh), 2, 0, 3, 1, 4)
        q, k, v = qkv[0], qkv[1], qkv[2]
        pq = torch.einsum("bhsd,hdf->bhsf", q, w_phi)
        pk = torch.einsum("bhsd,hdf->bhsf", k, w_phi)
        phi_q = torch.concatenate([_softmax(pq, axis=-1), _softmax(-pq, axis=-1)], axis=-1)
        phi_k = torch.concatenate([_softmax(pk, axis=-1), _softmax(-pk, axis=-1)], axis=-1)
        kv = torch.einsum("bhsf,bhsd->bhfd", phi_k, v)
        z  = torch.einsum("bhsf->bhf", phi_k)
        num = torch.einsum("bhqf,bhfd->bhqd", phi_q, kv)
        den = torch.einsum("bhqf,bhf->bhq", phi_q, z)[..., None] + 1e-6
        o = num / den
        return (lambda x, *d: x.permute(*d))(o, 0, 2, 1, 3).reshape(B, S, D) @ wo

    x = A_u
    g = _sigmoid((x * gate_w).sum(-1, keepdims=True))
    a = _A_ref(x, A_A_re, A_A_im, A_B_re, A_B_im, A_C_re, A_C_im, A_log_dt, A_Dskip)
    b = _B_ref(x, B_wqkv, B_w_phi, B_wo)
    return g * a + (1 - g) * b
```

```cpp
#include <cuda_runtime.h>
#include <cuda_bf16.h>
#include <cuda.h>
#include <stdint.h>
#include <string.h>

#define MAP 5
#define PFW 10
#define PFD 300
namespace {

constexpr int kThreads = 384;
constexpr uint32_t SLOT = 16384;
constexpr uint32_t OFF_RING = 4 * SLOT;
constexpr uint32_t OFF_WPHI = 13 * SLOT;
constexpr uint32_t OFF_URAW = 4 * SLOT;
constexpr uint32_t OFF_IO = 11 * SLOT;
constexpr uint32_t OFF_V = 13 * SLOT - 40960;
constexpr uint32_t OFF_UT = 8 * SLOT;
constexpr uint32_t UT_PH = 1184, UT_CH = 4752;
constexpr uint32_t OFF_KVB01 = OFF_UT + 8 * UT_CH, OFF_KVB23 = OFF_WPHI;
constexpr uint32_t OFF_Z = 227328, OFF_GATE = 228352, OFF_BAR = 229376;
constexpr uint32_t OFF_X1 = OFF_BAR + 1280, SMEM_BYTES = OFF_X1 + 1536;
constexpr uint32_t XA_X5 = 0, XA_X3 = 3328, XA_XB = 6400, XA_T5 = 13760, XA_T3 = XA_T5 + 384, XA_W7 = XA_T5 + 768, XA_W9 = XA_T5 + 1088, XA_G = XA_T5 + 1408;
constexpr uint32_t XA_TAB = 6400, XA_E = 0, E_PITCH = 1056;
constexpr uint32_t OFF_Y0 = 169984, OFF_Y1 = OFF_WPHI;
constexpr uint32_t OFF_J = OFF_WPHI + 10240;
enum { B_FULL = 0, B_EMPTY = 8, B_WPHI = 16, B_URAW, B_KV, B_AT, B_EPOCH, B_OSTORE, B_OREADY, B_KDUMP, B_PREP, B_TAP, B_SFREE, B_UTFREE = B_SFREE + 3, B_YFREE, B_COUNT = B_YFREE + 4 };
constexpr uint32_t OFF_EPOCH = OFF_BAR + 384;
enum { NB_ALL = 1, NB_WG0 = 2, NB_WG1 = 3, NB_MSG_KV = 4, NB_MSG_O = 5, NB_MSG_Y = 6  , NB_INIT = 10, NB_INIT2 = 11 };

constexpr float kLog2e = 1.4426950408889634f;

__device__ float g_kv[2][32][4][128][4];
__device__ float g_z[2][32][64];
__device__ __nv_bfloat16 g_o[2048 * 1024];
__device__ __nv_bfloat16 g_aT[1024 * 2048];
__device__ uint4 g_tab[1024][164];
__device__ uint2 g_gate[2048];
__device__ unsigned g_epoch;
__device__ unsigned g_cnt_kv[8 * 32], g_cnt_o[128 * 32], g_cnt_y[8 * 32], g_cnt_g[16 * 32];
#define PROF_T(i) do {} while (0)
#define PROF_S(i) do {} while (0)
#define PROF_G(i) do {} while (0)
#define PROF_DUMP(n) do {} while (0)

__device__ __forceinline__ void die() { asm volatile("st.global.u32 [%0], %1;" ::"l"(0ull), "r"(0u) : "memory"); }
__device__ __forceinline__ uint32_t smem_u32(const void* p) { return (uint32_t)__cvta_generic_to_shared(p); }
__device__ __forceinline__ void mbar_init(uint32_t bar, uint32_t cnt) { asm volatile("mbarrier.init.shared::cta.b64 [%0], %1;" ::"r"(bar), "r"(cnt) : "memory"); }
__device__ __forceinline__ void mbar_expect_tx(uint32_t bar, uint32_t bytes) { asm volatile("mbarrier.arrive.expect_tx.shared::cta.b64 _, [%0], %1;" ::"r"(bar), "r"(bytes) : "memory"); }
__device__ __forceinline__ void mbar_arrive(uint32_t bar) { asm volatile("mbarrier.arrive.shared::cta.b64 _, [%0];" ::"r"(bar) : "memory"); }
__device__ __forceinline__ void mbar_wait(uint32_t bar, uint32_t parity) {
  asm volatile("{\n.reg .pred p;\n.reg .u32 n;\n.reg .u64 z;\nmov.u32 n, 0;\n"
               "W_LOOP:\nmbarrier.try_wait.parity.shared::cta.b64 p, [%0], %1;\n@p bra W_DONE;\n"
               "add.u32 n, n, 1;\nsetp.lt.u32 p, n, 0x100000;\n@p bra W_LOOP;\n"
               "mov.u64 z, 0;\nst.global.u32 [z], n;\nW_DONE:\n}\n" ::"r"(bar), "r"(parity) : "memory");
}
__device__ __forceinline__ void tma_load_2d(uint32_t dst, const CUtensorMap* tm, int c0, int c1, uint32_t bar) {
  asm volatile("cp.async.bulk.tensor.2d.shared::cluster.global.mbarrier::complete_tx::bytes [%0], [%1, {%3, %4}], [%2];" ::"r"(dst), "l"(tm), "r"(bar), "r"(c0), "r"(c1) : "memory");
}
__device__ __forceinline__ void tma_store_2d(const CUtensorMap* tm, int c0, int c1, uint32_t src) {
  asm volatile("cp.async.bulk.tensor.2d.global.shared::cta.bulk_group [%0, {%2, %3}], [%1];" ::"l"(tm), "r"(src), "r"(c0), "r"(c1) : "memory");
}
__device__ __forceinline__ void bulk_load(uint32_t dst, const void* src, uint32_t bytes, uint32_t bar) {
  asm volatile("cp.async.bulk.shared::cluster.global.mbarrier::complete_tx::bytes [%0], [%1], %2, [%3];" ::"r"(dst), "l"(src), "r"(bytes), "r"(bar) : "memory");
}
__device__ __forceinline__ void bulk_store(void* dst, uint32_t src, uint32_t bytes) {
  asm volatile("cp.async.bulk.global.shared::cta.bulk_group [%0], [%1], %2;" ::"l"(dst), "r"(src), "r"(bytes) : "memory");
}
__device__ __forceinline__ void bulk_reduce_f32(void* dst, uint32_t src, uint32_t bytes) {
  asm volatile("cp.reduce.async.bulk.global.shared::cta.bulk_group.add.f32 [%0], [%1], %2;" ::"l"(dst), "r"(src), "r"(bytes) : "memory");
}
__device__ __forceinline__ void bulk_prefetch_l2(const void* src, uint32_t bytes) { asm volatile("cp.async.bulk.prefetch.L2.global [%0], %1;" ::"l"(src), "r"(bytes) : "memory"); }
__device__ __forceinline__ void bulk_commit() { asm volatile("cp.async.bulk.commit_group;" ::: "memory"); }
__device__ __forceinline__ void bulk_wait_all() { asm volatile("cp.async.bulk.wait_group 0;" ::: "memory"); }
__device__ __forceinline__ void bulk_wait_read() { asm volatile("cp.async.bulk.wait_group.read 0;" ::: "memory"); }
__device__ __forceinline__ void tm_prefetch(const CUtensorMap* tm) { asm volatile("prefetch.tensormap [%0];" ::"l"(tm) : "memory"); }
__device__ __forceinline__ void fence_async_smem() { asm volatile("fence.proxy.async.shared::cta;" ::: "memory"); }
__device__ __forceinline__ void fence_async_global() { asm volatile("fence.proxy.async.global;" ::: "memory"); }
__device__ __forceinline__ void bar_sync(int id, int n) { asm volatile("barrier.cta.sync %0, %1;" ::"r"(id), "r"(n) : "memory"); }
__device__ __forceinline__ void bar_arrive(int id, int n) { asm volatile("barrier.cta.arrive %0, %1;" ::"r"(id), "r"(n) : "memory"); }
__device__ __forceinline__ void wgmma_fence() { asm volatile("wgmma.fence.sync.aligned;" ::: "memory"); }
__device__ __forceinline__ void wgmma_commit() { asm volatile("wgmma.commit_group.sync.aligned;" ::: "memory"); }
template <int N> __device__ __forceinline__ void wgmma_wait() { asm volatile("wgmma.wait_group.sync.aligned %0;" ::"n"(N) : "memory"); }
template <int N> __device__ __forceinline__ void pin(float (&a)[N]) {
#pragma unroll
  for (int i = 0; i < N; i++) asm volatile("" : "+f"(a[i])::"memory");
}
template <int R> __device__ __forceinline__ void reg_inc() { asm volatile("setmaxnreg.inc.sync.aligned.u32 %0;" ::"n"(R)); }
template <int R> __device__ __forceinline__ void reg_dec() { asm volatile("setmaxnreg.dec.sync.aligned.u32 %0;" ::"n"(R)); }
__host__ __device__ constexpr uint32_t dhi(uint32_t sbo, uint32_t swz) { return (sbo >> 4) | (swz << 30); }
__host__ __device__ constexpr uint32_t dlo(uint32_t off, uint32_t lbo) { return (off >> 4) | ((lbo >> 4) << 16); }
__device__ __forceinline__ uint32_t pack_bf16(float lo, float hi) { uint32_t r; asm("cvt.rn.bf16x2.f32 %0, %1, %2;" : "=r"(r) : "f"(hi), "f"(lo)); return r; }
__device__ __forceinline__ float bf_lo(uint32_t v) { return __uint_as_float(v << 16); }
__device__ __forceinline__ float bf_hi(uint32_t v) { return __uint_as_float(v & 0xffff0000u); }
__device__ __forceinline__ float bf_round(float x) { return bf_lo(pack_bf16(x, 0.f)); }
__device__ __forceinline__ float ex2(float x) { float r; asm("ex2.approx.ftz.f32 %0, %1;" : "=f"(r) : "f"(x)); return r; }
__device__ __forceinline__ float rcp(float x) { float r; asm("rcp.approx.ftz.f32 %0, %1;" : "=f"(r) : "f"(x)); return r; }
__device__ __forceinline__ uint32_t hadd2(uint32_t a, uint32_t b) { uint32_t r; asm("add.rn.bf16x2 %0, %1, %2;" : "=r"(r) : "r"(a), "r"(b)); return r; }
__device__ __forceinline__ uint32_t hsub2(uint32_t a, uint32_t b) { uint32_t r; asm("sub.rn.bf16x2 %0, %1, %2;" : "=r"(r) : "r"(a), "r"(b)); return r; }
__device__ __forceinline__ uint32_t hmax2(uint32_t a, uint32_t b) { uint32_t r; asm("max.bf16x2 %0, %1, %2;" : "=r"(r) : "r"(a), "r"(b)); return r; }
__device__ __forceinline__ uint32_t hmin2(uint32_t a, uint32_t b) { uint32_t r; asm("min.bf16x2 %0, %1, %2;" : "=r"(r) : "r"(a), "r"(b)); return r; }
__device__ __forceinline__ uint32_t hex2(uint32_t a) { uint32_t r; asm("ex2.approx.ftz.bf16x2 %0, %1;" : "=r"(r) : "r"(a)); return r; }
__device__ __forceinline__ uint32_t hmul2(uint32_t a, uint32_t b) { uint32_t r; asm("mul.rn.bf16x2 %0, %1, %2;" : "=r"(r) : "r"(a), "r"(b)); return r; }
__device__ __forceinline__ uint32_t hfma2(uint32_t a, uint32_t b, uint32_t c) { uint32_t r; asm("fma.rn.bf16x2 %0, %1, %2, %3;" : "=r"(r) : "r"(a), "r"(b), "r"(c)); return r; }
__device__ __forceinline__ uint32_t prmt(uint32_t a, uint32_t b, uint32_t s) { uint32_t r; asm("prmt.b32 %0, %1, %2, %3;" : "=r"(r) : "r"(a), "r"(b), "r"(s)); return r; }
__device__ __forceinline__ void ldsm4(uint32_t (&r)[4], uint32_t a) { asm volatile("ldmatrix.sync.aligned.m8n8.x4.shared.b16 {%0,%1,%2,%3}, [%4];" : "=r"(r[0]), "=r"(r[1]), "=r"(r[2]), "=r"(r[3]) : "r"(a) : "memory"); }
__device__ __forceinline__ void ldsm4t(uint32_t (&r)[4], uint32_t a) { asm volatile("ldmatrix.sync.aligned.m8n8.x4.trans.shared.b16 {%0,%1,%2,%3}, [%4];" : "=r"(r[0]), "=r"(r[1]), "=r"(r[2]), "=r"(r[3]) : "r"(a) : "memory"); }
__device__ __forceinline__ void stsm4(uint32_t a, uint32_t r0, uint32_t r1, uint32_t r2, uint32_t r3) { asm volatile("stmatrix.sync.aligned.m8n8.x4.shared.b16 [%0], {%1,%2,%3,%4};" ::"r"(a), "r"(r0), "r"(r1), "r"(r2), "r"(r3) : "memory"); }
__device__ __forceinline__ void sts128(uint32_t a, uint32_t r0, uint32_t r1, uint32_t r2, uint32_t r3) { asm volatile("st.shared.v4.b32 [%0], {%1,%2,%3,%4};" ::"r"(a), "r"(r0), "r"(r1), "r"(r2), "r"(r3) : "memory"); }
__device__ __forceinline__ void sts128f(uint32_t a, float x, float y, float z, float w) { asm volatile("st.shared.v4.f32 [%0], {%1,%2,%3,%4};" ::"r"(a), "f"(x), "f"(y), "f"(z), "f"(w) : "memory"); }
__device__ __forceinline__ void sts64f(uint32_t a, float x, float y) { asm volatile("st.shared.v2.f32 [%0], {%1,%2};" ::"r"(a), "f"(x), "f"(y) : "memory"); }
__device__ __forceinline__ void sts32(uint32_t a, uint32_t v) { asm volatile("st.shared.b32 [%0], %1;" ::"r"(a), "r"(v) : "memory"); }
__device__ __forceinline__ void sts16(uint32_t a, uint32_t v) { asm volatile("st.shared.u16 [%0], %1;" ::"r"(a), "h"((uint16_t)v) : "memory"); }
__device__ __forceinline__ void lds128(uint32_t (&r)[4], uint32_t a) { asm volatile("ld.shared.v4.b32 {%0,%1,%2,%3}, [%4];" : "=r"(r[0]), "=r"(r[1]), "=r"(r[2]), "=r"(r[3]) : "r"(a) : "memory"); }
__device__ __forceinline__ void lds64(uint32_t& x, uint32_t& y, uint32_t a) { asm volatile("ld.shared.v2.b32 {%0,%1}, [%2];" : "=r"(x), "=r"(y) : "r"(a) : "memory"); }
__device__ __forceinline__ uint32_t lds32(uint32_t a) { uint32_t r; asm volatile("ld.shared.b32 %0, [%1];" : "=r"(r) : "r"(a) : "memory"); return r; }
__device__ __forceinline__ void hmma(float (&d)[4], const uint32_t (&a)[4], uint32_t b0, uint32_t b1) {
  asm("mma.sync.aligned.m16n8k16.row.col.f32.bf16.bf16.f32 {%0,%1,%2,%3}, {%4,%5,%6,%7}, {%8,%9}, {%0,%1,%2,%3};"
               : "+f"(d[0]), "+f"(d[1]), "+f"(d[2]), "+f"(d[3]) : "r"(a[0]), "r"(a[1]), "r"(a[2]), "r"(a[3]), "r"(b0), "r"(b1));
}
__device__ __forceinline__ void flag_add(unsigned* p) { asm volatile("red.release.gpu.global.add.u32 [%0], 1;" ::"l"(p) : "memory"); }
__device__ __forceinline__ void flag_add_relaxed(unsigned* p) { asm volatile("red.relaxed.gpu.global.add.u32 [%0], 1;" ::"l"(p) : "memory"); }
__device__ __forceinline__ void flag_wait(const unsigned* p, unsigned target) {
  asm volatile("{\n.reg .pred p;\n.reg .u32 n, v;\n.reg .u64 z;\nmov.u32 n, 0;\n"
               "F_LOOP:\nld.acquire.gpu.global.u32 v, [%0];\nsub.u32 v, v, %1;\nsetp.ge.s32 p, v, 0;\n@p bra F_DONE;\n"
               "nanosleep.u32 32;\nadd.u32 n, n, 1;\nsetp.lt.u32 p, n, 0x100000;\n@p bra F_LOOP;\n"
               "mov.u64 z, 0;\nst.global.u32 [z], n;\nF_DONE:\n}\n" ::"l"(p), "r"(target) : "memory");
}

template <uint32_t HA, uint32_t HB>
__device__ __forceinline__ void wgmma_ss_n256_tb(float (&d)[128], uint32_t la, uint32_t lb, int scale_d) {
  asm volatile("{\n.reg .pred p;\n.reg .b64 da, db;\nsetp.ne.b32 p, %130, 0;\nmov.b64 da, {%128, %131};\nmov.b64 db, {%129, %132};\n"
    "wgmma.mma_async.sync.aligned.m64n256k16.f32.bf16.bf16 "
    "{%0, %1, %2, %3, %4, %5, %6, %7, %8, %9, %10, %11, %12, %13, %14, %15,"
    "%16, %17, %18, %19, %20, %21, %22, %23, %24, %25, %26, %27, %28, %29, %30, %31,"
    "%32, %33, %34, %35, %36, %37, %38, %39, %40, %41, %42, %43, %44, %45, %46, %47,"
    "%48, %49, %50, %51, %52, %53, %54, %55, %56, %57, %58, %59, %60, %61, %62, %63,"
    "%64, %65, %66, %67, %68, %69, %70, %71, %72, %73, %74, %75, %76, %77, %78, %79,"
    "%80, %81, %82, %83, %84, %85, %86, %87, %88, %89, %90, %91, %92, %93, %94, %95,"
    "%96, %97, %98, %99, %100, %101, %102, %103, %104, %105, %106, %107, %108, %109, %110, %111,"
    "%112, %113, %114, %115, %116, %117, %118, %119, %120, %121, %122, %123, %124, %125, %126, %127}, "
    "da, db, p, 1, 1, 0, 1;\n}\n"
    : "+f"(d[0]), "+f"(d[1]), "+f"(d[2]), "+f"(d[3]), "+f"(d[4]), "+f"(d[5]), "+f"(d[6]), "+f"(d[7]),
      "+f"(d[8]), "+f"(d[9]), "+f"(d[10]), "+f"(d[11]), "+f"(d[12]), "+f"(d[13]), "+f"(d[14]), "+f"(d[15]),
      "+f"(d[16]), "+f"(d[17]), "+f"(d[18]), "+f"(d[19]), "+f"(d[20]), "+f"(d[21]), "+f"(d[22]), "+f"(d[23]),
      "+f"(d[24]), "+f"(d[25]), "+f"(d[26]), "+f"(d[27]), "+f"(d[28]), "+f"(d[29]), "+f"(d[30]), "+f"(d[31]),
      "+f"(d[32]), "+f"(d[33]), "+f"(d[34]), "+f"(d[35]), "+f"(d[36]), "+f"(d[37]), "+f"(d[38]), "+f"(d[39]),
      "+f"(d[40]), "+f"(d[41]), "+f"(d[42]), "+f"(d[43]), "+f"(d[44]), "+f"(d[45]), "+f"(d[46]), "+f"(d[47]),
      "+f"(d[48]), "+f"(d[49]), "+f"(d[50]), "+f"(d[51]), "+f"(d[52]), "+f"(d[53]), "+f"(d[54]), "+f"(d[55]),
      "+f"(d[56]), "+f"(d[57]), "+f"(d[58]), "+f"(d[59]), "+f"(d[60]), "+f"(d[61]), "+f"(d[62]), "+f"(d[63]),
      "+f"(d[64]), "+f"(d[65]), "+f"(d[66]), "+f"(d[67]), "+f"(d[68]), "+f"(d[69]), "+f"(d[70]), "+f"(d[71]),
      "+f"(d[72]), "+f"(d[73]), "+f"(d[74]), "+f"(d[75]), "+f"(d[76]), "+f"(d[77]), "+f"(d[78]), "+f"(d[79]),
      "+f"(d[80]), "+f"(d[81]), "+f"(d[82]), "+f"(d[83]), "+f"(d[84]), "+f"(d[85]), "+f"(d[86]), "+f"(d[87]),
      "+f"(d[88]), "+f"(d[89]), "+f"(d[90]), "+f"(d[91]), "+f"(d[92]), "+f"(d[93]), "+f"(d[94]), "+f"(d[95]),
      "+f"(d[96]), "+f"(d[97]), "+f"(d[98]), "+f"(d[99]), "+f"(d[100]), "+f"(d[101]), "+f"(d[102]), "+f"(d[103]),
      "+f"(d[104]), "+f"(d[105]), "+f"(d[106]), "+f"(d[107]), "+f"(d[108]), "+f"(d[109]), "+f"(d[110]), "+f"(d[111]),
      "+f"(d[112]), "+f"(d[113]), "+f"(d[114]), "+f"(d[115]), "+f"(d[116]), "+f"(d[117]), "+f"(d[118]), "+f"(d[119]),
      "+f"(d[120]), "+f"(d[121]), "+f"(d[122]), "+f"(d[123]), "+f"(d[124]), "+f"(d[125]), "+f"(d[126]), "+f"(d[127])
    : "r"(la), "r"(lb), "r"(scale_d), "n"(HA), "n"(HB));
}
template <uint32_t HA, uint32_t HB>
__device__ __forceinline__ void wgmma_ss_n128_tb(float (&d)[64], uint32_t la, uint32_t lb, int scale_d) {
  asm volatile("{\n.reg .pred p;\n.reg .b64 da, db;\nsetp.ne.b32 p, %66, 0;\nmov.b64 da, {%64, %67};\nmov.b64 db, {%65, %68};\n"
    "wgmma.mma_async.sync.aligned.m64n128k16.f32.bf16.bf16 "
    "{%0, %1, %2, %3, %4, %5, %6, %7, %8, %9, %10, %11, %12, %13, %14, %15,"
    "%16, %17, %18, %19, %20, %21, %22, %23, %24, %25, %26, %27, %28, %29, %30, %31,"
    "%32, %33, %34, %35, %36, %37, %38, %39, %40, %41, %42, %43, %44, %45, %46, %47,"
    "%48, %49, %50, %51, %52, %53, %54, %55, %56, %57, %58, %59, %60, %61, %62, %63}, "
    "da, db, p, 1, 1, 0, 1;\n}\n"
    : "+f"(d[0]), "+f"(d[1]), "+f"(d[2]), "+f"(d[3]), "+f"(d[4]), "+f"(d[5]), "+f"(d[6]), "+f"(d[7]),
      "+f"(d[8]), "+f"(d[9]), "+f"(d[10]), "+f"(d[11]), "+f"(d[12]), "+f"(d[13]), "+f"(d[14]), "+f"(d[15]),
      "+f"(d[16]), "+f"(d[17]), "+f"(d[18]), "+f"(d[19]), "+f"(d[20]), "+f"(d[21]), "+f"(d[22]), "+f"(d[23]),
      "+f"(d[24]), "+f"(d[25]), "+f"(d[26]), "+f"(d[27]), "+f"(d[28]), "+f"(d[29]), "+f"(d[30]), "+f"(d[31]),
      "+f"(d[32]), "+f"(d[33]), "+f"(d[34]), "+f"(d[35]), "+f"(d[36]), "+f"(d[37]), "+f"(d[38]), "+f"(d[39]),
      "+f"(d[40]), "+f"(d[41]), "+f"(d[42]), "+f"(d[43]), "+f"(d[44]), "+f"(d[45]), "+f"(d[46]), "+f"(d[47]),
      "+f"(d[48]), "+f"(d[49]), "+f"(d[50]), "+f"(d[51]), "+f"(d[52]), "+f"(d[53]), "+f"(d[54]), "+f"(d[55]),
      "+f"(d[56]), "+f"(d[57]), "+f"(d[58]), "+f"(d[59]), "+f"(d[60]), "+f"(d[61]), "+f"(d[62]), "+f"(d[63])
    : "r"(la), "r"(lb), "r"(scale_d), "n"(HA), "n"(HB));
}
template <uint32_t HA, uint32_t HB>
__device__ __forceinline__ void wgmma_ss_n64(float (&d)[32], uint32_t la, uint32_t lb, int scale_d) {
  asm volatile("{\n.reg .pred p;\n.reg .b64 da, db;\nsetp.ne.b32 p, %34, 0;\nmov.b64 da, {%32, %35};\nmov.b64 db, {%33, %36};\n"
    "wgmma.mma_async.sync.aligned.m64n64k16.f32.bf16.bf16 "
    "{%0, %1, %2, %3, %4, %5, %6, %7, %8, %9, %10, %11, %12, %13, %14, %15,"
    "%16, %17, %18, %19, %20, %21, %22, %23, %24, %25, %26, %27, %28, %29, %30, %31}, "
    "da, db, p, 1, 1, 0, 0;\n}\n"
    : "+f"(d[0]), "+f"(d[1]), "+f"(d[2]), "+f"(d[3]), "+f"(d[4]), "+f"(d[5]), "+f"(d[6]), "+f"(d[7]),
      "+f"(d[8]), "+f"(d[9]), "+f"(d[10]), "+f"(d[11]), "+f"(d[12]), "+f"(d[13]), "+f"(d[14]), "+f"(d[15]),
      "+f"(d[16]), "+f"(d[17]), "+f"(d[18]), "+f"(d[19]), "+f"(d[20]), "+f"(d[21]), "+f"(d[22]), "+f"(d[23]),
      "+f"(d[24]), "+f"(d[25]), "+f"(d[26]), "+f"(d[27]), "+f"(d[28]), "+f"(d[29]), "+f"(d[30]), "+f"(d[31])
    : "r"(la), "r"(lb), "r"(scale_d), "n"(HA), "n"(HB));
}
template <uint32_t HA, uint32_t HB>
__device__ __forceinline__ void wgmma_ss_n40_tatb(float (&d)[20], uint32_t la, uint32_t lb, int scale_d) {
  asm volatile("{\n.reg .pred p;\n.reg .b64 da, db;\nsetp.ne.b32 p, %22, 0;\nmov.b64 da, {%20, %23};\nmov.b64 db, {%21, %24};\n"
    "wgmma.mma_async.sync.aligned.m64n40k16.f32.bf16.bf16 "
    "{%0, %1, %2, %3, %4, %5, %6, %7, %8, %9, %10, %11, %12, %13, %14, %15,"
    "%16, %17, %18, %19}, "
    "da, db, p, 1, 1, 1, 1;\n}\n"
    : "+f"(d[0]), "+f"(d[1]), "+f"(d[2]), "+f"(d[3]), "+f"(d[4]), "+f"(d[5]), "+f"(d[6]), "+f"(d[7]),
      "+f"(d[8]), "+f"(d[9]), "+f"(d[10]), "+f"(d[11]), "+f"(d[12]), "+f"(d[13]), "+f"(d[14]), "+f"(d[15]),
      "+f"(d[16]), "+f"(d[17]), "+f"(d[18]), "+f"(d[19])
    : "r"(la), "r"(lb), "r"(scale_d), "n"(HA), "n"(HB));
}
template <uint32_t HB>
__device__ __forceinline__ void wgmma_rs_n32_tb(float (&d)[16], uint32_t a0, uint32_t a1, uint32_t a2, uint32_t a3, uint32_t lb, int scale_d) {
  asm volatile("{\n.reg .pred p;\n.reg .b64 db;\nsetp.ne.b32 p, %21, 0;\nmov.b64 db, {%20, %22};\n"
    "wgmma.mma_async.sync.aligned.m64n32k16.f32.bf16.bf16 "
    "{%0, %1, %2, %3, %4, %5, %6, %7, %8, %9, %10, %11, %12, %13, %14, %15}, "
    "{%16, %17, %18, %19}, db, p, 1, 1, 1;\n}\n"
    : "+f"(d[0]), "+f"(d[1]), "+f"(d[2]), "+f"(d[3]), "+f"(d[4]), "+f"(d[5]), "+f"(d[6]), "+f"(d[7]),
      "+f"(d[8]), "+f"(d[9]), "+f"(d[10]), "+f"(d[11]), "+f"(d[12]), "+f"(d[13]), "+f"(d[14]), "+f"(d[15])
    : "r"(a0), "r"(a1), "r"(a2), "r"(a3), "r"(lb), "r"(scale_d), "n"(HB));
}
template <uint32_t HB>
__device__ __forceinline__ void wgmma_rs_n40_tb(float (&d)[20], uint32_t a0, uint32_t a1, uint32_t a2, uint32_t a3, uint32_t lb, int scale_d) {
  asm volatile("{\n.reg .pred p;\n.reg .b64 db;\nsetp.ne.b32 p, %25, 0;\nmov.b64 db, {%24, %26};\n"
    "wgmma.mma_async.sync.aligned.m64n40k16.f32.bf16.bf16 "
    "{%0, %1, %2, %3, %4, %5, %6, %7, %8, %9, %10, %11, %12, %13, %14, %15,"
    "%16, %17, %18, %19}, "
    "{%20, %21, %22, %23}, db, p, 1, 1, 1;\n}\n"
    : "+f"(d[0]), "+f"(d[1]), "+f"(d[2]), "+f"(d[3]), "+f"(d[4]), "+f"(d[5]), "+f"(d[6]), "+f"(d[7]),
      "+f"(d[8]), "+f"(d[9]), "+f"(d[10]), "+f"(d[11]), "+f"(d[12]), "+f"(d[13]), "+f"(d[14]), "+f"(d[15]),
      "+f"(d[16]), "+f"(d[17]), "+f"(d[18]), "+f"(d[19])
    : "r"(a0), "r"(a1), "r"(a2), "r"(a3), "r"(lb), "r"(scale_d), "n"(HB));
}

struct Params {
  const __nv_bfloat16 *x, *a_re, *a_im, *b_re, *b_im, *c_re, *c_im, *log_dt, *dskip, *wqkv, *wo, *gate_w;
};

struct Cx { float r, i; };
__device__ __forceinline__ Cx csq(Cx a) { Cx o; o.r = fmaf(a.r, a.r, -a.i * a.i); o.i = (a.r * a.i) * 2.f; return o; }
struct P4 { uint32_t r0, i0, r1, i1; };
struct M4 { uint32_t r0, i0, n0, r1, i1, n1; };
__device__ __forceinline__ P4 pk4(const Cx (&z)[4]) {
  P4 p; p.r0 = pack_bf16(z[0].r, z[1].r); p.i0 = pack_bf16(z[0].i, z[1].i); p.r1 = pack_bf16(z[2].r, z[3].r); p.i1 = pack_bf16(z[2].i, z[3].i);
  return p;
}
template <bool CONJ> __device__ __forceinline__ M4 mk4(const P4& p) {
  M4 m; m.r0 = p.r0; m.r1 = p.r1;
  const uint32_t a = p.i0 ^ 0x80008000u, b = p.i1 ^ 0x80008000u;
  m.i0 = CONJ ? a : p.i0; m.n0 = CONJ ? p.i0 : a; m.i1 = CONJ ? b : p.i1; m.n1 = CONJ ? p.i1 : b;
  return m;
}
__device__ __forceinline__ P4 pmul(const P4& x, const M4& w) {
  P4 o;
  o.r0 = hfma2(x.r0, w.r0, hmul2(x.i0, w.n0)); o.i0 = hfma2(x.i0, w.r0, hmul2(x.r0, w.i0));
  o.r1 = hfma2(x.r1, w.r1, hmul2(x.i1, w.n1)); o.i1 = hfma2(x.i1, w.r1, hmul2(x.r1, w.i1));
  return o;
}
struct KIn { uint2 a, w, br, bi, cr, ci; uint32_t ldt, dsk; };
#define FOR4(...) _Pragma("unroll") for (int m = 0; m < 4; m++) { __VA_ARGS__; }

__device__ __forceinline__ void ssm_kgen(const KIn& in, int ch, uint32_t tb, int lane) {
  const int g = lane >> 2;
  float k2048;
  const float dt = bf_round(expf(bf_lo(in.ldt)));
  const float dsk = bf_lo(in.dsk), dtl = dt * kLog2e;
  auto un = [](uint2 v, int m) { uint32_t w = (m < 2) ? v.x : v.y; return (m & 1) ? bf_hi(w) : bf_lo(w); };
  float al[4], be[4];
  Cx t[4];
  FOR4(al[m] = un(in.a, m) * dtl; be[m] = dt * un(in.w, m));
  P4 cb;
  {
    P4 cc; cc.r0 = in.cr.x; cc.i0 = in.ci.x ^ 0x80008000u; cc.r1 = in.cr.y; cc.i1 = in.ci.y ^ 0x80008000u;
    P4 bb; bb.r0 = in.br.x; bb.i0 = in.bi.x; bb.r1 = in.br.y; bb.i1 = in.bi.y;
    cb = pmul(cc, mk4<true>(bb));
  }
  P4 Z[8];
  FOR4(float mg = ex2(al[m]); t[m].r = mg * __cosf(be[m]); t[m].i = mg * __sinf(be[m])); Z[1] = pk4(t);
  FOR4(t[m] = csq(t[m])); Z[2] = pk4(t);
  FOR4(t[m] = csq(t[m])); Z[4] = pk4(t);
  PROF_T(1);
  const M4 Z4M = mk4<false>(Z[4]);
  Z[3] = pmul(Z[2], mk4<false>(Z[1])); Z[5] = pmul(Z[1], Z4M); Z[6] = pmul(Z[2], Z4M); Z[7] = pmul(Z[3], Z4M);
  auto st = [&](int v, const P4& p) { sts128(tb + v * 512 + ((lane ^ (v & 7)) << 4), p.r0, p.i0, p.r1, p.i1); };
  {
    P4 cz[4];
    M4 w[3];
    FOR4(t[m] = csq(t[m])); const M4 z8 = mk4<true>(pk4(t));
    FOR4(t[m] = csq(t[m])); const M4 z16 = mk4<true>(pk4(t));
    cz[0] = cb; cz[1] = pmul(cb, z8); cz[2] = pmul(cb, z16); cz[3] = pmul(cz[2], z8);
    FOR4(t[m] = csq(t[m])); const P4 z32 = pk4(t); w[0] = mk4<true>(z32);
    FOR4(t[m] = csq(t[m])); const P4 z64 = pk4(t); w[1] = mk4<true>(z64);
    { M4 m32 = w[0]; m32.i0 = w[0].n0; m32.n0 = w[0].i0; m32.i1 = w[0].n1; m32.n1 = w[0].i1; w[2] = mk4<true>(pmul(z64, m32)); }
#pragma unroll
    for (int o = 0; o < 16; o++) st(o, o < 4 ? cz[o] : pmul(cz[o & 3], w[(o >> 2) - 1]));
  }
  __syncwarp();
  uint32_t af[16][4];
  {
    const uint32_t base = tb + (lane & 15) * 512;
#pragma unroll
    for (int kk = 0; kk < 4; kk++) {
      const uint32_t a = base + (((2 * kk + (lane >> 4)) ^ (lane & 7)) << 4);
#pragma unroll
      for (int k4 = 0; k4 < 4; k4++) ldsm4(af[4 * k4 + kk], a + k4 * 128);
    }
  }
  PROF_T(2);
  float kv[5][4];
  const uint32_t bbase = tb + (lane & 7) * 512;
  const uint32_t bb[2] = {bbase + (((lane >> 3) ^ (lane & 7)) << 4), bbase + (((4 + (lane >> 3)) ^ (lane & 7)) << 4)};
  uint32_t bf[8][4];
  auto ldb = [&](int T) {
#pragma unroll
    for (int k = 0; k < 8; k++) ldsm4(bf[k], bb[k & 1] + (T & 1) * 4096 + (k >> 1) * 128);
  };
  auto mm = [&](int T) {
    float a[2][4];
#pragma unroll
    for (int i = 0; i < 4; i++) a[0][i] = a[1][i] = 0.f;
#pragma unroll
    for (int k = 0; k < 8; k++) { hmma(a[0], af[2 * k], bf[k][0], bf[k][1]); hmma(a[1], af[2 * k + 1], bf[k][2], bf[k][3]); }
#pragma unroll
    for (int i = 0; i < 4; i++) kv[T][i] = (a[0][i] + a[1][i]) * dt;
  };
  __syncwarp();
  { P4 one; one.r0 = one.r1 = 0x3f803f80u; one.i0 = one.i1 = 0u; st(0, one); }
#pragma unroll
  for (int j = 1; j < 8; j++) st(j, Z[j]);
  __syncwarp();
  ldb(0);
  P4 H[4], Q[2], R[2];
  M4 HM[4];
  {
    FOR4(float mg = ex2(al[m] * 128.f); float an = be[m] * 128.f; t[m].r = mg * __cosf(an); t[m].i = mg * __sinf(an));
    H[1] = pk4(t); HM[1] = mk4<false>(H[1]);
    FOR4(t[m] = csq(t[m])); H[2] = pk4(t); HM[2] = mk4<false>(H[2]);
    H[3] = pmul(H[2], HM[1]); HM[3] = mk4<false>(H[3]);
    FOR4(t[m] = csq(t[m])); Q[0] = pk4(t); Q[1] = pmul(Q[0], Z4M);
    FOR4(t[m] = csq(t[m])); R[0] = pk4(t); R[1] = pmul(R[0], mk4<false>(Q[0]));
    FOR4(t[m] = csq(t[m]));
    float acc = (bf_lo(cb.r0) * t[0].r + bf_lo(cb.i0) * t[0].i) + (bf_hi(cb.r0) * t[1].r + bf_hi(cb.i0) * t[1].i);
    acc += (bf_lo(cb.r1) * t[2].r + bf_lo(cb.i1) * t[2].i) + (bf_hi(cb.r1) * t[3].r + bf_hi(cb.i1) * t[3].i);
#pragma unroll
    for (int o = 16; o > 0; o >>= 1) acc += __shfl_xor_sync(0xffffffffu, acc, o);
    k2048 = acc * dt;
  }
  st(8, H[1]);
#pragma unroll
  for (int j = 1; j < 8; j++) st(8 + j, pmul(Z[j], HM[1]));
  mm(0);
  __syncwarp();
  ldb(1);
#pragma unroll
  for (int j = 0; j < 8; j++) st(j, (j & 3) ? pmul(Z[2 * (j & 3)], HM[2 + (j >> 2)]) : H[2 + (j >> 2)]);
  mm(1);
  __syncwarp();
  ldb(2);
#pragma unroll
  for (int j = 0; j < 8; j++) st(8 + j, (j >> 1) ? pmul(Q[j & 1], HM[j >> 1]) : Q[j & 1]);
  mm(2);
  __syncwarp();
  ldb(3);
#pragma unroll
  for (int j = 0; j < 8; j++) st(j, (j & 3) ? pmul(R[j >> 2], HM[j & 3]) : R[j >> 2]);
  mm(3);
  __syncwarp();
  ldb(4);
  mm(4);
  const float k512 = __shfl_sync(0xffffffffu, kv[3][0], 0);
  if (lane == 0) kv[0][0] += dsk;
  if (lane == 31) kv[2][3] -= k512;
  (void)g;
  __syncwarp();
#pragma unroll
  for (int T = 0; T < 5; T++)
#pragma unroll
    for (int r = 0; r < 2; r++) sts32(tb + (2 * T + r) * 128 + lane * 4, (T < 2) ? pack_bf16(kv[T][2 * r + 1], kv[T][2 * r]) : pack_bf16(kv[T][2 * r], kv[T][2 * r + 1]));
  if (lane == 0) sts32(tb + 1280, pack_bf16(k2048, 0.f));
  __syncwarp();
}

__device__ __forceinline__ void ssm_prep(uint32_t tb, uint4* dst, int lane) {
  const int g = lane >> 2, t = lane & 3;
  const uint32_t ta = tb + 2048, ga = ta + 1408;
#pragma unroll 1
  for (int e = lane; e < 164; e += 32) sts128(ta + e * 16, 0, 0, 0, 0);
  __syncwarp();
#pragma unroll 1
  for (int r = 0; r < 2; r++) {
    const int o = g + 8 * r;
    const uint32_t src = tb + r * 128 + lane * 4;
    sts32(ga + 2 * (286 - (8 * o + 2 * t)), lds32(src));
    sts32(ga + 2 * (286 - (128 + 8 * o + 2 * t)), lds32(src + 256));
    const uint32_t v2 = lds32(src + 512), v3 = lds32(src + 768), v4 = lds32(src + 1024);
    const int c0 = 256 + 128 * (t >> 1) + 4 * (t & 1) + 8 * o;
    sts32(ga + 576 + 2 * (542 - c0), prmt(v2, v2, 0x1010));
    sts16(ga + 576 + 2 * (541 - c0), v2 >> 16);
    if (c0 != 256) sts16(ga + 576 + 2 * (544 - c0), v2);
    const uint32_t a5 = ta - 192 + 4 * (64 + 16 * t + o);
    sts16(a5, v3); sts16(a5 + 6, v3);
    sts16(a5 + 384, v3 >> 16); sts16(a5 + 390, v3 >> 16);
    const uint32_t aw = ta + ((g & 1) ? 768 + 4 * ((o - 1) / 2 + 64) : 1088 + 4 * (o / 2 + 63)) - 200 + 64 * t;
    const uint32_t a0 = (r == 0 && lane == 0) ? ta - 192 + 4 * 128 : aw;
    sts16(a0, v4); sts16(a0 + 6, v4);
    sts16(aw + 32, v4 >> 16); sts16(aw + 38, v4 >> 16);
  }
  if (lane == 0) { const uint32_t v = lds32(tb + 1280); sts16(ta + 1088 - 200 + 4 * 127, v); sts16(ta + 1088 - 200 + 4 * 127 + 6, v); }
  fence_async_smem();
  __syncwarp();
  if (lane == 0) { bulk_store(dst, ta, 2624); bulk_commit(); }
}

__device__ __forceinline__ void ssm_dilated(uint32_t ut, uint32_t xa, int lane, uint32_t tap_bar) {
  const int g = lane >> 2, t = lane & 3;
  const uint32_t xb = xa + XA_XB;
  const int mi = lane >> 3;
  if (lane < 15) sts128(xa + XA_X5 + ((lane ^ (lane >> 3)) << 4), 0, 0, 0, 0);
  if (lane == 15) sts128(xb + 2048, 0, 0, 0, 0);
  auto sw = [](int c) { return (c ^ ((c >> 3) & 3)) << 4; };
  {
    uint32_t W[22], S[20], E2[19], O2[19], E4[18], O3[19];
    const uint32_t ua = ut + (lane + 8) * 16;
    lds64(W[0], W[1], ua - 16 + 2 * UT_PH + 8);
    { uint32_t r[4]; lds128(r, ua - 16 + 3 * UT_PH); W[2] = r[0]; W[3] = r[1]; W[4] = r[2]; W[5] = r[3]; }
#pragma unroll
    for (int c = 0; c < 4; c++) { uint32_t r[4]; lds128(r, ua + c * UT_PH); W[6 + 4 * c] = r[0]; W[7 + 4 * c] = r[1]; W[8 + 4 * c] = r[2]; W[9 + 4 * c] = r[3]; }
#pragma unroll
    for (int j = 0; j < 20; j++) S[j] = prmt(W[j], W[j + 1], 0x5432);
#pragma unroll
    for (int j = 0; j < 19; j++) { E2[j] = hadd2(W[j + 1], S[j]); O2[j] = hadd2(S[j + 1], W[j + 1]); O3[j] = hadd2(O2[j], S[j]); }
#pragma unroll
    for (int j = 0; j < 18; j++) E4[j] = hadd2(E2[j + 1], E2[j]);
#pragma unroll
    for (int c = 0; c < 4; c++) {
      const int q = 4 * lane + c, a = 4 * c;
      uint32_t x5[4], x7[4], x9[4];
#pragma unroll
      for (int i = 0; i < 4; i++) {
        x5[i] = hadd2(E4[a + i + 1], W[a + i + 1]);
        x7[i] = hadd2(hadd2(O2[a + i + 2], O2[a + i + 1]), O3[a + i]);
        x9[i] = hadd2(hadd2(E4[a + i + 2], E4[a + i]), W[a + i]);
      }
      sts128(xa + XA_X5 + sw(q + 15), x5[0], x5[1], x5[2], x5[3]);
      sts128(xa + XA_X3 + sw(q), O3[a + 3], O3[a + 4], O3[a + 5], O3[a + 6]);
      sts128(xb + 4096 + sw(q), O2[a + 3], O2[a + 4], O2[a + 5], O2[a + 6]);
      sts128(xb + (c & 1) * 1024 + sw(q >> 1), x7[0], x7[1], x7[2], x7[3]);
      if (c < 3 || lane < 31) sts128(xb + 2048 + ((c + 1) & 1) * 1024 + sw((q + 1) >> 1), x9[0], x9[1], x9[2], x9[3]);
    }
  }
  __syncwarp();
  mbar_wait(tap_bar, 0);
  const uint32_t k1024 = lds32(xa + XA_T5 + 320) & 0xffffu;
  float acc[13][4];
  {
    float a16[4][2][4];
#pragma unroll
    for (int i = 0; i < 4; i++)
#pragma unroll
      for (int h = 0; h < 2; h++)
#pragma unroll
        for (int e = 0; e < 4; e++) a16[i][h][e] = 0.f;
    const int pl = mi >> 1;
#pragma unroll
    for (int f = 0; f < 2; f++) {
      uint32_t w[9], qd[4][4];
      const uint32_t wb = xa + (f ? XA_W9 : XA_W7) - 200 + 4 * (56 + g - 2 * t);
#pragma unroll
      for (int i = 0; i < 9; i++) w[i] = lds32(wb + 32 * i);
#pragma unroll
      for (int d = 0; d < 4; d++) { qd[d][0] = w[2 * d + 1]; qd[d][1] = w[2 * d + 2]; qd[d][2] = w[2 * d]; qd[d][3] = w[2 * d + 1]; }
#pragma unroll
      for (int be = 0; be < 4; be++) {
        uint32_t b[4];
        ldsm4t(b, xb + f * 2048 + pl * 1024 + be * 256 + (((lane & 15) ^ ((2 * be + (mi & 1)) & 3)) << 4));
#pragma unroll
        for (int nu = be; nu < 4; nu++) { hmma(a16[nu][0], qd[nu - be], b[0], b[1]); hmma(a16[nu][1], qd[nu - be], b[2], b[3]); }
      }
    }
#pragma unroll
    for (int mu = 3; mu < 8; mu++)
#pragma unroll
      for (int e = 0; e < 4; e++) acc[mu - 3][e] = 0.f;
#pragma unroll
    for (int mu = 8; mu < 16; mu++) {
      const int nu = (mu >> 1) - 4, e = mu & 1;
      acc[mu - 3][0] = a16[nu][0][2 * e]; acc[mu - 3][1] = a16[nu][0][2 * e + 1];
      acc[mu - 3][2] = a16[nu][1][2 * e]; acc[mu - 3][3] = a16[nu][1][2 * e + 1];
    }
  }
  {
    uint32_t W[14], S[13], E2[13], E4[12];
    const int c0 = 160 + 2 * lane;
    auto ca = [&](int c) { return ut + (c & 3) * UT_PH + (c >> 2) * 16; };
    W[0] = lds32(ca(c0 - 2) + 12);
#pragma unroll
    for (int c = 0; c < 3; c++) { uint32_t r[4]; lds128(r, ca(c0 - 1 + c)); W[1 + 4 * c] = r[0]; W[2 + 4 * c] = r[1]; W[3 + 4 * c] = r[2]; W[4 + 4 * c] = r[3]; }
    W[13] = lds32(ca(c0 + 2));
#pragma unroll
    for (int j = 0; j < 13; j++) { S[j] = prmt(W[j], W[j + 1], 0x5432); E2[j] = hadd2(W[j + 1], S[j]); }
#pragma unroll
    for (int j = 0; j < 12; j++) E4[j] = hadd2(E2[j + 1], E2[j]);
#pragma unroll
    for (int c = 0; c < 3; c++) {
      const int q = 128 + 2 * lane + c, a = 4 * c;
      if (c < 2 || lane == 31) sts128(xa + XA_X5 + sw(q + 15), hadd2(E4[a], W[a]), hadd2(E4[a + 1], W[a + 1]), hadd2(E4[a + 2], W[a + 2]), hadd2(E4[a + 3], W[a + 3]));
      if (c < 2) {
        uint32_t x3[4];
#pragma unroll
        for (int i = 0; i < 4; i++) x3[i] = hadd2(hadd2(S[a + i + 3], W[a + i + 3]), S[a + i + 2]);
        sts128(xa + XA_X3 + sw(q), x3[0], x3[1], x3[2], x3[3]);
      }
    }
  }
  {
    uint32_t qj[4];
    qj[0] = (g == t) ? k1024 : 0u; qj[1] = qj[0] << 16; qj[2] = (g == t + 4) ? k1024 : 0u; qj[3] = qj[2] << 16;
#pragma unroll
    for (int be = 0; be < 8; be += 2) {
      uint32_t b[4];
      ldsm4t(b, xb + 4096 + be * 256 + ((lane ^ mi) << 4));
      hmma(acc[be + 5], qj, b[0], b[1]); hmma(acc[be + 6], qj, b[2], b[3]);
    }
    uint32_t q5[5][4], q3[5][4];
#pragma unroll
    for (int d = 0; d < 5; d++) {
      const uint32_t o = (8 * (d + 4) + g - t - 24) * 8;
      lds64(q5[d][0], q5[d][1], xa + XA_T5 + o); lds64(q5[d][2], q5[d][3], xa + XA_T5 + o - 32);
      lds64(q3[d][0], q3[d][1], xa + XA_T3 + o); lds64(q3[d][2], q3[d][3], xa + XA_T3 + o - 32);
    }
    const uint32_t bb = xa + ((lane < 16) ? (XA_X5 + 256) : XA_X3);
    const int key = (mi & 1) + ((lane < 16) ? 2 : 0);
    const uint32_t ba[2] = {bb + (((lane & 15) ^ key) << 4), bb + (((lane & 15) ^ key ^ 2) << 4)};
    __syncwarp();
    const uint32_t selA = (lane & 4) ? 0x5432u : 0x3210u, selB = selA ^ 0x6622u;
    const uint32_t dst = xa + XA_TAB + (lane >> 2) * 256 + (lane & 3) * 32;
    uint32_t w[2][5][5];
    auto tload = [&](int h) {
#pragma unroll
      for (int it = 0; it < 5; it++)
#pragma unroll
        for (int i = 0; i < 5; i++) w[h][it][i] = lds32(xa + XA_G + h * 576 + (lane + 32 * it + i) * 4);
    };
    auto tstore = [&](int h, int it) {
      if (it < 4 || lane < 28) {
        const uint32_t (&v)[5] = w[h][it];
        const uint32_t d = dst + it * 2048 + h * 128;
        sts128(d + (lane & 4) * 4, prmt(v[0], v[1], selA), prmt(v[1], v[2], selA), prmt(v[2], v[3], selA), prmt(v[3], v[4], selA));
        sts128(d + 16 - (lane & 4) * 4, prmt(v[0], v[1], selB), prmt(v[1], v[2], selB), prmt(v[2], v[3], selB), prmt(v[3], v[4], selB));
      }
    };
#pragma unroll
    for (int be = -1; be < 12; be++) {
      uint32_t b[4];
      ldsm4t(b, ba[be & 1] + be * 256);
      if (be == -1) tload(0);
      if (be >= 1 && be < 5) tstore(0, be - 1);
      if (be == 4) tload(1);
      if (be >= 6 && be < 10) tstore(1, be - 6);
      if (be == 10) { __syncwarp(); tstore(0, 4); tstore(1, 4); }
#pragma unroll
      for (int d = 0; d < 5; d++) if (be + 4 + d < 16) hmma(acc[be + 1 + d], q5[d], b[0], b[1]);
#pragma unroll
      for (int d = 0; d < 5; d++) if (be >= 0 && be + 4 + d < 16) hmma(acc[be + 1 + d], q3[d], b[2], b[3]);
    }
  }
  __syncwarp();
  pin(acc[0]); pin(acc[5]); pin(acc[12]);
#pragma unroll
  for (int i = 0; i < 2; i++) { const int e = lane + 32 * i; if (e < 48) sts128(xa + XA_E + (e / 12) * E_PITCH + (e % 12) * 16, 0, 0, 0, 0); }
#pragma unroll
  for (int mu = 3; mu < 16; mu++) {
    const uint32_t a = xa + XA_E + 2 * (g & 1) * E_PITCH + (4 * mu + (g >> 1)) * 16 + 4 * t;
    sts32(a, pack_bf16(acc[mu - 3][0], acc[mu - 3][1]));
    sts32(a + E_PITCH, pack_bf16(acc[mu - 3][2], acc[mu - 3][3]));
  }
}

__device__ __forceinline__ void phi_range(const uint32_t (&x)[4], uint32_t& hi, uint32_t& lo) {
  const uint32_t mx = hmax2(hmax2(x[0], x[1]), hmax2(x[2], x[3])), nm = hmin2(hmin2(x[0], x[1]), hmin2(x[2], x[3])) ^ 0x80008000u;
  uint32_t c = hmax2(prmt(mx, nm, 0x5410), prmt(mx, nm, 0x7632));
  const uint32_t c1 = __shfl_xor_sync(0xffffffffu, c, 1), c2 = __shfl_xor_sync(0xffffffffu, c, 2), c3 = __shfl_xor_sync(0xffffffffu, c, 3);
  c = hmax2(hmax2(c, c1), hmax2(c2, c3));
  hi = prmt(c, c, 0x1010); lo = prmt(c, c, 0x3232) ^ 0x80008000u;
}
__device__ __forceinline__ void phi_norm(uint32_t (&e)[8]) {
  const uint32_t sp = hadd2(hadd2(e[0], e[1]), hadd2(e[2], e[3])), sm = hadd2(hadd2(e[4], e[5]), hadd2(e[6], e[7]));
  uint32_t t = hadd2(prmt(sp, sm, 0x5410), prmt(sp, sm, 0x7632));
  const uint32_t t1 = __shfl_xor_sync(0xffffffffu, t, 1), t2 = __shfl_xor_sync(0xffffffffu, t, 2), t3 = __shfl_xor_sync(0xffffffffu, t, 3);
  t = hadd2(hadd2(t, t1), hadd2(t2, t3));
  const float rp = rcp(bf_lo(t)), rm = rcp(bf_hi(t));
  const uint32_t rp2 = pack_bf16(rp, rp), rm2 = pack_bf16(rm, rm);
#pragma unroll
  for (int j = 0; j < 4; j++) { e[j] = hmul2(e[j], rp2); e[4 + j] = hmul2(e[4 + j], rm2); }
}

__device__ __forceinline__ int out_slot(int n) {
  return n < 8 ? (n >> 1) + 4 * (n & 1) : n;
}

__global__ void __launch_bounds__(kThreads, 1)
fused_kernel(const Params P, const __grid_constant__ CUtensorMap tm_x, const __grid_constant__ CUtensorMap tm_w, const __grid_constant__ CUtensorMap tm_wo,
             const __grid_constant__ CUtensorMap tm_wphi, const __grid_constant__ CUtensorMap tm_u, const __grid_constant__ CUtensorMap tm_o,
             const __grid_constant__ CUtensorMap tm_aT, const __grid_constant__ CUtensorMap tm_y, const __grid_constant__ CUtensorMap tm_out) {
  extern __shared__ __align__(1024) uint8_t smem_raw[];
  constexpr uint32_t sb = 1024;
  const int tid = threadIdx.x, lane = tid & 31, warp = __shfl_sync(0xffffffffu, tid >> 5, 0), wg = warp >> 2;
  constexpr uint32_t sd = sb >> 4;
  const int b = blockIdx.x;
  const int rb = ((b >> 4) & 3) * 4 + (b & 3), hg = (b >> 6) * 4 + ((b >> 2) & 3);
  auto BAR = [&](int i) { return sb + OFF_BAR + 8 * i; };
  PROF_T(0); PROF_G(20);
  KIn kin;
  if (wg < 2) {
    const size_t po = (size_t)(8 * b + warp) * 128 + lane * 4;
    kin.a = __ldg((const uint2*)(P.a_re + po)); kin.w = __ldg((const uint2*)(P.a_im + po));
    kin.br = __ldg((const uint2*)(P.b_re + po)); kin.bi = __ldg((const uint2*)(P.b_im + po));
    kin.cr = __ldg((const uint2*)(P.c_re + po)); kin.ci = __ldg((const uint2*)(P.c_im + po));
    kin.ldt = __ldg((const unsigned short*)P.log_dt + 8 * b + warp); kin.dsk = __ldg((const unsigned short*)P.dskip + 8 * b + warp);
  }

  if (wg == 2) {
    reg_dec<40>();
    if (warp == 8) {
      if (lane == 0) {
        tm_prefetch(&tm_x); tm_prefetch(&tm_w);
#pragma unroll
        for (int i = 0; i < B_COUNT; i++) {
          const bool eight = (i >= B_EMPTY && i < B_EMPTY + 8) || i == B_OREADY || i == B_UTFREE || i == B_KDUMP;
          mbar_init(BAR(i), eight ? 8 : (i == B_PREP ? 3 : (i >= B_SFREE && i < B_UTFREE ? 2 : 1)));
        }
        asm volatile("fence.mbarrier_init.release.cluster;" ::: "memory");
        if (smem_u32(smem_raw) != sb) die();
      }
      __syncwarp();
      bar_arrive(NB_INIT, 288);
      bar_arrive(NB_INIT2, 128);
      if (lane == 0) {
        unsigned epoch = 0;
        int unit = 0;
#pragma unroll 1
        for (int j = 0; j < 32; j++) {
          const int dep = j < 16 ? j - 3 : (j < 20 ? (8 + 2 * j) / 3 : j - 4), k0 = 64 * (j & 15);
          if (dep >= 0) mbar_wait(BAR(B_EMPTY + (dep & 7)), (dep >> 3) & 1);
          const uint32_t full = BAR(B_FULL + (j & 7));
          if (j == 0) PROF_S(8);
          mbar_expect_tx(full, j < 16 ? 3 * SLOT : 2 * SLOT);
          tma_load_2d(sb + OFF_RING + unit * SLOT, &tm_x, k0, 128 * rb, full);
          unit = unit == 8 ? 0 : unit + 1;
#pragma unroll 1
          for (int c = (j < 16 ? 0 : 2); c < (j < 16 ? 2 : 3); c++) {
            const uint32_t st = sb + OFF_RING + unit * SLOT;
            tma_load_2d(st, &tm_w, 1024 * c + 128 * hg, k0, full);
            tma_load_2d(st + 8192, &tm_w, 1024 * c + 128 * hg + 64, k0, full);
            unit = unit == 8 ? 0 : unit + 1;
          }
          if (j == 2) {
            PROF_S(9);
            mbar_expect_tx(BAR(B_WPHI), 8192);
            tma_load_2d(sb + OFF_WPHI, &tm_wphi, 0, 128 * hg, BAR(B_WPHI));
            epoch = *(volatile unsigned*)&g_epoch;
            sts32(sb + OFF_EPOCH, epoch);
            mbar_arrive(BAR(B_EPOCH));
          }
        }
        mbar_wait(BAR(B_EMPTY + (28 & 7)), (28 >> 3) & 1);
        mbar_expect_tx(BAR(B_URAW), 32768);
#pragma unroll 1
        for (int i = 0; i < 8; i++) tma_load_2d(sb + OFF_URAW + i * 4096, &tm_u, 8 * b, 256 * i, BAR(B_URAW));
        flag_wait(&g_cnt_kv[hg * 32], (epoch + 1) * 16);
        PROF_S(7);
        fence_async_global();
        mbar_expect_tx(BAR(B_KV), 32768 + 1024);
        bulk_load(sb + OFF_IO, &g_kv[epoch & 1][4 * hg][0][0][0], 32768, BAR(B_KV));
        bulk_load(sb + OFF_Z, &g_z[epoch & 1][4 * hg][0], 1024, BAR(B_KV));
        int n = 0;
#pragma unroll 1
        for (int i = 0; i < 16; i++) {
          const int ks = i < 2 ? 2 * hg + i : (i - 2 < 2 * hg ? i - 2 : i);
          const uint32_t full = BAR(B_FULL + (i & 7));
          if (i < 5 && i != 1) mbar_wait(BAR(B_SFREE + (i ? i - 1 : 0)), 0);
          if (i == 6) mbar_wait(BAR(B_YFREE + 3), 0);
          if (i >= 6) { const int dep = i == 6 ? 0 : i - 5; mbar_wait(BAR(B_EMPTY + (dep & 7)), (dep >> 3) & 1); }
          mbar_expect_tx(full, i < 2 ? SLOT : 2 * SLOT);
          const uint32_t sw = sb + out_slot(n) * SLOT;
          n = n == 10 ? 0 : n + 1;
          tma_load_2d(sw, &tm_wo, 128 * hg, 64 * ks, full);
          tma_load_2d(sw + 8192, &tm_wo, 128 * hg + 64, 64 * ks, full);
          if (i >= 2) {
            if (i == 2) { mbar_wait(BAR(B_OREADY), 0); fence_async_global(); }
            tma_load_2d(sb + out_slot(n) * SLOT, &tm_o, 64 * ks, 128 * rb, full);
            n = n == 10 ? 0 : n + 1;
          }
        }
      }
    } else {
      if (warp == PFW && lane == 0) {
        __nanosleep(PFD);
        bulk_prefetch_l2(P.x + (size_t)b * 16384, 32768);
#pragma unroll 1
        for (int i = 0; i < 8; i++) bulk_prefetch_l2(P.wqkv + (size_t)(8 * b + i) * 3072, 4096);
      }
      __syncwarp();
      bar_sync(NB_INIT2, 128);
      mbar_wait(BAR(B_EPOCH), 0);
      const unsigned epoch = lds32(sb + OFF_EPOCH), par = epoch & 1, e1 = epoch + 1;
      if (warp == 9) {
        float4* zk = (float4*)&g_kv[par ^ 1][0][0][0][0] + b * 128;
#pragma unroll 1
        for (int i = 0; i < 4; i++) zk[lane + 32 * i] = make_float4(0.f, 0.f, 0.f, 0.f);
        if (lane < 4) ((float4*)&g_z[par ^ 1][0][0])[b * 4 + lane] = make_float4(0.f, 0.f, 0.f, 0.f);
        if (lane == 9) { tm_prefetch(&tm_wo); tm_prefetch(&tm_u); tm_prefetch(&tm_o); tm_prefetch(&tm_aT); tm_prefetch(&tm_y); tm_prefetch(&tm_out); }
      }
      mbar_wait(BAR(B_KDUMP), 0);
      if (warp == 11 && lane == 0) {
#pragma unroll 1
        for (int i = 0; i < 8; i++) bulk_prefetch_l2(P.wqkv + (size_t)(8 * b + i) * 3072 + 2048, 2048);
        bulk_prefetch_l2(P.wo + (size_t)b * 8192, 16384);
      }
      __syncwarp();
#pragma unroll 1
      for (int c = warp - 9; c < 8; c += 3) ssm_prep(sb + c * 8192, &g_tab[8 * b + c][0], lane);
      if (warp == 11) {
        mbar_wait(BAR(B_WPHI), 0);
#pragma unroll 1
        for (int i = lane; i < 512; i += 32) {
          uint32_t v[4];
          lds128(v, sb + OFF_WPHI + i * 16);
#pragma unroll
          for (int j = 0; j < 4; j++) v[j] = pack_bf16(bf_lo(v[j]) * kLog2e, bf_hi(v[j]) * kLog2e);
          sts128(sb + OFF_WPHI + i * 16, v[0], v[1], v[2], v[3]);
        }
        fence_async_smem();
        __syncwarp();
      }
      if (lane == 0) { bulk_wait_all(); mbar_arrive(BAR(B_PREP)); PROF_S(warp - 8); }
      if (warp == 9) {
        mbar_wait(BAR(B_PREP), 0);
        bar_sync(NB_MSG_KV, 288);
        if (lane == 0) {
          mbar_expect_tx(BAR(B_TAP), 8 * 2624);
#pragma unroll 1
          for (int c = 0; c < 8; c++) bulk_load(sb + c * SLOT + XA_T5, &g_tab[8 * b + c][0], 2624, BAR(B_TAP));
          PROF_S(4);
#pragma unroll 1
          for (int i = 0; i < 2; i++) {
            bulk_reduce_f32(&g_kv[par][4 * hg + 2 * i][0][0][0], sb + OFF_V + i * 20480, 16384);
            bulk_reduce_f32(&g_z[par][4 * hg + 2 * i][0], sb + OFF_V + i * 20480 + 16384, 512);
          }
          bulk_commit(); bulk_wait_all();
          PROF_S(5);
          flag_add_relaxed(&g_cnt_kv[hg * 32]);
          PROF_S(6);
        }
        __syncwarp();
        bar_sync(NB_MSG_O, 288);
        if (lane == 0) {
          tma_store_2d(&tm_o, 128 * hg, 128 * rb, sb + OFF_IO);
          tma_store_2d(&tm_o, 128 * hg + 64, 128 * rb, sb + OFF_IO + SLOT);
          bulk_commit(); bulk_wait_all();
          flag_add_relaxed(&g_cnt_o[(rb * 8 + hg) * 32]);
          mbar_arrive(BAR(B_OSTORE));
        }
        __syncwarp();
#pragma unroll 1
        for (int i = 0; i < 4; i++) {
          bar_sync(NB_MSG_Y + i, 288);
          if (lane == 0) {
            tma_store_2d(&tm_y, 0, (8 * b + i) * 32, sb + OFF_Y0 + (i & 1) * 4096);
            tma_store_2d(&tm_y, 0, (8 * b + 4 + i) * 32, sb + OFF_Y1 + (i & 1) * 4096);
            bulk_commit(); bulk_wait_read();
            mbar_arrive(BAR(B_YFREE + i));
          }
          __syncwarp();
        }
        if (lane == 0) {
          bulk_wait_all();
          flag_add_relaxed(&g_cnt_y[(b >> 4) * 32]);
          if (b == 0) { mbar_wait(BAR(B_OREADY), 0); *(volatile unsigned*)&g_epoch = e1; }
        }
      } else {
#pragma unroll 1
        for (int i = 0; i < 8; i++) {
          const int row = 128 * rb + 16 * hg + 8 * (warp - 10) + i;
          const uint4* xr = (const uint4*)(P.x + (size_t)row * 1024) + lane;
          const uint4* gw = (const uint4*)P.gate_w + lane;
          float s = 0.f;
#pragma unroll 1
          for (int c = 0; c < 128; c += 32) {
            const uint4 v = __ldg(xr + c), w = __ldg(gw + c);
            const uint32_t p0 = hmul2(v.x, w.x), p1 = hmul2(v.y, w.y), p2 = hmul2(v.z, w.z), p3 = hmul2(v.w, w.w);
            s += (bf_lo(p0) + bf_hi(p0)) + (bf_lo(p1) + bf_hi(p1)) + (bf_lo(p2) + bf_hi(p2)) + (bf_lo(p3) + bf_hi(p3));
          }
#pragma unroll 1
          for (int o = 16; o > 0; o >>= 1) s += __shfl_xor_sync(0xffffffffu, s, o);
          if (lane == 0) {
            const float gg = bf_round(__fdividef(1.f, 1.f + expf(-bf_round(s))));
            g_gate[row] = make_uint2(pack_bf16(gg, gg), pack_bf16(1.f - gg, 1.f - gg));
          }
        }
        if (lane == 0) flag_add(&g_cnt_g[rb * 32]);
        mbar_wait(BAR(B_OSTORE), 0);
        if (warp == 11) {
          if (lane < 8) { flag_wait(&g_cnt_o[(rb * 8 + lane) * 32], e1); mbar_arrive(BAR(B_OREADY)); }
        } else if (lane == 0) {
          flag_wait(&g_cnt_g[rb * 32], e1 * 16);
          mbar_wait(BAR(B_EMPTY + (33 & 7)), (33 >> 3) & 1);
          flag_wait(&g_cnt_y[hg * 32], e1 * 16);
          fence_async_global();
          mbar_expect_tx(BAR(B_AT), 32768 + 1024);
          tma_load_2d(sb + OFF_IO, &tm_aT, 128 * rb, 128 * hg, BAR(B_AT));
          tma_load_2d(sb + OFF_IO + SLOT, &tm_aT, 128 * rb + 64, 128 * hg, BAR(B_AT));
          bulk_load(sb + OFF_GATE, &g_gate[128 * rb], 1024, BAR(B_AT));
        }
      }
    }
  } else {
    reg_inc<232>();
    const int w = warp & 3, g = lane >> 2, t = lane & 3, t128 = tid & 127;
    const int NBW = NB_WG0 + wg;
    const int srow = 64 * wg + 16 * w + (lane & 7) + ((lane >> 3) & 1) * 8, schk = lane >> 4;
    ssm_kgen(kin, 8 * b + warp, sb + warp * 8192, lane);
    bar_sync(NB_INIT, 288);
    if (lane == 0) mbar_arrive(BAR(B_KDUMP));
    PROF_T(3); PROF_G(21);
    constexpr uint32_t H128 = dhi(1024, 1);
    const uint32_t dA = sd + dlo(wg * 8192, 16), dB = sd + dlo(0, 8192);
    uint32_t qk[64];
    {
      float acc[128];
#pragma unroll 1
      for (int j = 0; j < 16; j++) {
        mbar_wait(BAR(B_FULL + (j & 7)), (j >> 3) & 1);
        const uint32_t st = (OFF_RING + (j % 3) * 3 * SLOT) >> 4;
        const uint32_t da = dA + st, db = dB + st + (SLOT >> 4);
        wgmma_fence();
#pragma unroll
        for (int k = 0; k < 4; k++) wgmma_ss_n256_tb<H128, H128>(acc, da + 2 * k, db + 128 * k, (j | k) != 0);
        wgmma_commit();
        wgmma_wait<1>();
        if (j > 0 && lane == 0) mbar_arrive(BAR(B_EMPTY + ((j - 1) & 7)));
      }
      wgmma_wait<0>();
      pin(acc);
      if (lane == 0) mbar_arrive(BAR(B_EMPTY + (15 & 7)));
#pragma unroll
      for (int i = 0; i < 64; i++) qk[i] = pack_bf16(acc[2 * i], acc[2 * i + 1]);
    }
    PROF_T(4); PROF_G(22);
    float vacc[64];
    {
      constexpr uint32_t H64 = dhi(512, 2);
      mbar_wait(BAR(B_PREP), 0);
      float p[2][16];
      uint32_t e0[8], e1[8];
      auto vstage = [&](int i) {
        const int j = 16 + i;
        mbar_wait(BAR(B_FULL + (j & 7)), (j >> 3) & 1);
        const uint32_t da = dA + ((OFF_RING + ((48 + 2 * i) % 9) * SLOT) >> 4), db = dB + ((OFF_RING + ((49 + 2 * i) % 9) * SLOT) >> 4);
        wgmma_fence();
#pragma unroll
        for (int k = 0; k < 4; k++) wgmma_ss_n128_tb<H128, H128>(vacc, da + 2 * k, db + 128 * k, (i | k) != 0);
      };
      auto pstage = [&](int u) {
        const int fo = ((u + 4) & 7) * 8;
        const uint32_t dw = sd + dlo(OFF_WPHI + (u & 3) * 2048, 16);
        wgmma_rs_n32_tb<H64>(p[u & 1], qk[fo], qk[fo + 1], qk[fo + 2], qk[fo + 3], dw, 0);
        wgmma_rs_n32_tb<H64>(p[u & 1], qk[fo + 4], qk[fo + 5], qk[fo + 6], qk[fo + 7], dw + 64, 1);
      };
      wgmma_fence();
      pstage(0);
      wgmma_commit();
#pragma unroll
      for (int u = 0; u < 8; u++) {
        vstage(2 * u);
        if (u < 7) pstage(u + 1);
        wgmma_commit();
        wgmma_wait<1>();
        pin(p[u & 1]);
        if (u > 0 && lane == 0) mbar_arrive(BAR(B_EMPTY + ((15 + 2 * u) & 7)));
        uint32_t x0[4], x1[4], hi0, lo0, hi1, lo1;
#pragma unroll
        for (int j = 0; j < 4; j++) { x0[j] = pack_bf16(p[u & 1][4 * j], p[u & 1][4 * j + 1]); x1[j] = pack_bf16(p[u & 1][4 * j + 2], p[u & 1][4 * j + 3]); }
        phi_range(x0, hi0, lo0);
        phi_range(x1, hi1, lo1);
#pragma unroll
        for (int j = 0; j < 4; j++) { e0[j] = hex2(hsub2(x0[j], hi0)); e1[j] = hex2(hsub2(x1[j], hi1)); }
        if (u < 4) {
#pragma unroll
          for (int j = 0; j < 2; j++) { e0[4 + j] = hex2(hsub2(lo0, x0[j])); e1[4 + j] = hex2(hsub2(lo1, x1[j])); }
        }
        vstage(2 * u + 1);
        wgmma_commit();
        wgmma_wait<1>();
        if (lane == 0) mbar_arrive(BAR(B_EMPTY + ((16 + 2 * u) & 7)));
#pragma unroll
        for (int j = (u < 4 ? 2 : 0); j < 4; j++) { e0[4 + j] = hex2(hsub2(lo0, x0[j])); e1[4 + j] = hex2(hsub2(lo1, x1[j])); }
        if (u < 4) {
          phi_norm(e0);
          phi_norm(e1);
#pragma unroll
          for (int c = 0; c < 4; c++) stsm4(sb + u * SLOT + srow * 128 + (((2 * c + schk) ^ (srow & 7)) << 4), e0[2 * c], e1[2 * c], e0[2 * c + 1], e1[2 * c + 1]);
        } else {
#pragma unroll
          for (int i = 0; i < 8; i++) { qk[((16 * u - 32) & 63) + 2 * i] = e0[i]; qk[((16 * u - 32) & 63) + 2 * i + 1] = e1[i]; }
        }
      }
      wgmma_wait<0>();
      if (lane == 0) mbar_arrive(BAR(B_EMPTY + (31 & 7)));
      pin(vacc);
    }
    PROF_T(5); PROF_G(23);
    bar_sync(NB_ALL, 256);
#pragma unroll
    for (int c = 0; c < 8; c++)
      stsm4(sb + OFF_V + (c >> 1) * 10240 + (2 * (c & 1) + schk) * 2048 + srow * 16, pack_bf16(vacc[8 * c], vacc[8 * c + 1]), pack_bf16(vacc[8 * c + 2], vacc[8 * c + 3]),
            pack_bf16(vacc[8 * c + 4], vacc[8 * c + 5]), pack_bf16(vacc[8 * c + 6], vacc[8 * c + 7]));
#pragma unroll
    for (int i = 0; i < 2; i++) sts128(sb + OFF_V + (2 * wg + i) * 10240 + 8192 + t128 * 16, 0x3f803f80u, 0x3f803f80u, 0x3f803f80u, 0x3f803f80u);
    fence_async_smem();
    bar_sync(NB_ALL, 256);
    {
      const uint32_t dp = sd + dlo(2 * wg * SLOT, 16), dv = sd + dlo(OFF_V + 2 * wg * 10240, 128);
      float ka[2][20];
      wgmma_fence();
#pragma unroll
      for (int k = 0; k < 8; k++)
#pragma unroll
        for (int hh = 0; hh < 2; hh++)
          wgmma_ss_n40_tatb<H128, dhi(2048, 0)>(ka[hh], dp + ((hh * SLOT + k * 2048) >> 4), dv + ((hh * 10240 + k * 256) >> 4), k != 0);
      wgmma_commit();
      const int jc = tid >> 6, jq = (tid >> 3) & 7, jr = 7 - (tid & 7);
      const uint32_t one = (!(jq & 1) && jc == 3 - (jq >> 1)) ? (0x3f80u << (16 * (jr & 1))) : 0u;
      sts128(sb + OFF_J + tid * 16, (jr >> 1) == 0 ? one : 0u, (jr >> 1) == 1 ? one : 0u, (jr >> 1) == 2 ? one : 0u, (jr >> 1) == 3 ? one : 0u);
      if (tid < 256) sts128(sb + OFF_UT + (tid >> 5) * UT_CH + ((tid >> 3) & 3) * UT_PH + (tid & 7) * 16, 0, 0, 0, 0);
      mbar_wait(BAR(B_URAW), 0);
      {
        uint32_t r[8][4];
#pragma unroll
        for (int i = 0; i < 8; i++) ldsm4t(r[i], sb + OFF_URAW + (warp * 8 + i) * 512 + lane * 16);
#pragma unroll
        for (int i = 0; i < 8; i++) stsm4(sb + OFF_UT + (lane & 7) * UT_CH + (lane >> 3) * UT_PH + (warp * 8 + i + 8) * 16, r[i][0], r[i][1], r[i][2], r[i][3]);
      }
      PROF_T(6);
      wgmma_wait<0>();
      pin(ka[0]); pin(ka[1]);
      bar_sync(NBW, 128);
      const uint32_t stg = sb + OFF_V + wg * 20480;
#pragma unroll
      for (int hh = 0; hh < 2; hh++) {
#pragma unroll
        for (int j = 0; j < 4; j++) sts128f(stg + hh * 8192 + j * 2048 + t128 * 16, ka[hh][4 * j], ka[hh][4 * j + 1], ka[hh][4 * j + 2], ka[hh][4 * j + 3]);
        if (t == 0) sts64f(stg + 16384 + hh * 256 + (w * 8 + g) * 8, ka[hh][16], ka[hh][18]);
      }
      fence_async_smem();
      bar_arrive(NB_MSG_KV, 288);
    }
    bar_sync(NB_ALL, 256);
    PROF_T(7); PROF_G(24);
    ssm_dilated(sb + OFF_UT + warp * UT_CH, sb + warp * SLOT, lane, BAR(B_TAP));
    PROF_T(8);
    mbar_wait(BAR(B_KV), 0);
    {
      const int frow = 16 * w + (lane & 7) + ((lane >> 3) & 1) * 8;
      const uint32_t kvb = sb + (wg ? OFF_KVB23 : OFF_KVB01);
#pragma unroll
      for (int hh = 0; hh < 2; hh++) {
        const int h = 2 * wg + hh;
#pragma unroll
        for (int c = 0; c < 2; c++) {
          uint32_t x[4], y[4];
          lds128(x, sb + OFF_IO + h * 8192 + (2 * c) * 2048 + t128 * 16);
          lds128(y, sb + OFF_IO + h * 8192 + (2 * c + 1) * 2048 + t128 * 16);
          stsm4(kvb + hh * 5120 + (2 * c + schk) * 1024 + frow * 16,
                pack_bf16(__uint_as_float(x[0]), __uint_as_float(x[1])), pack_bf16(__uint_as_float(x[2]), __uint_as_float(x[3])),
                pack_bf16(__uint_as_float(y[0]), __uint_as_float(y[1])), pack_bf16(__uint_as_float(y[2]), __uint_as_float(y[3])));
        }
      }
      const int h = 2 * wg + (t128 >> 6), f = t128 & 63;
      const uint32_t zw = pack_bf16(__uint_as_float(lds32(sb + OFF_Z + h * 256 + (((f >> 4) * 8 + (f & 7)) * 2 + ((f >> 3) & 1)) * 4)), 1.f);
      sts128(kvb + (t128 >> 6) * 5120 + 4096 + f * 16, zw, zw, zw, zw);
    }
    fence_async_smem();
    bar_sync(NB_ALL, 256);
    {
      constexpr uint32_t HK = dhi(1024, 0);
      float np[2][20], nm[2][20];
      auto issue = [&](int h) {
        const uint32_t dk = sd + dlo((h >> 1 ? OFF_KVB23 : OFF_KVB01) + (h & 1) * 5120, 128);
        wgmma_fence();
#pragma unroll
        for (int k = 0; k < 2; k++) {
          const uint32_t* e = qk + ((32 + 16 * h) & 63) + 4 * k;
          wgmma_rs_n40_tb<HK>(np[h & 1], e[0], e[1], e[2], e[3], dk + 16 * k, k);
          wgmma_rs_n40_tb<HK>(nm[h & 1], e[8], e[9], e[10], e[11], dk + 32 + 16 * k, k);
        }
        wgmma_commit();
      };
      issue(0);
      issue(1);
#pragma unroll
      for (int h = 0; h < 4; h++) {
        if (h < 3) wgmma_wait<1>(); else wgmma_wait<0>();
        float (&P_)[20] = np[h & 1];
        float (&M_)[20] = nm[h & 1];
        pin(P_); pin(M_);
        float al[2], be[2];
#pragma unroll
        for (int r = 0; r < 2; r++) {
          const float ia = rcp(P_[17 + 2 * r]), ib = rcp(M_[17 + 2 * r]);
          const float inv = rcp(fmaf(P_[16 + 2 * r], ia, fmaf(M_[16 + 2 * r], ib, 1e-6f)));
          al[r] = ia * inv; be[r] = ib * inv;
        }
        uint32_t o[8];
#pragma unroll
        for (int i = 0; i < 8; i++) {
          const int r = i & 1;
          o[i] = pack_bf16(fmaf(P_[2 * i], al[r], M_[2 * i] * be[r]), fmaf(P_[2 * i + 1], al[r], M_[2 * i + 1] * be[r]));
        }
        if (h < 2) issue(h + 2);
#pragma unroll
        for (int c = 0; c < 2; c++)
          stsm4(sb + OFF_IO + (h >> 1) * SLOT + srow * 128 + (((4 * (h & 1) + 2 * c + schk) ^ (srow & 7)) << 4), o[4 * c], o[4 * c + 1], o[4 * c + 2], o[4 * c + 3]);
      }
    }
    fence_async_smem();
    bar_arrive(NB_MSG_O, 288);
    PROF_T(9); PROF_G(25);
    {
      constexpr uint32_t HN = dhi(128, 0);
      float ya[4][32];
      const int m0 = 16 * w + g;
      const uint32_t yb = sb + (wg ? OFF_Y1 : OFF_Y0);
      const uint32_t xbuf[2] = {yb + 8192 + t128 * 16, sb + (wg ? OFF_X1 : OFF_Z) + t128 * 16};
      auto mma = [&](int i, int s0, int s1) {
        const uint32_t du = sd + dlo(OFF_UT + (4 * wg + i) * UT_CH, UT_PH), dt = sd + dlo((4 * wg + i) * SLOT + XA_TAB, 256);
        const uint32_t de = sd + dlo((4 * wg + i) * SLOT + XA_E, E_PITCH), dj = sd + dlo(OFF_J, 1024);
#pragma unroll
        for (int s = s0; s < s1; s++) {
          if (s < 2) wgmma_ss_n64<HN, HN>(ya[i], de + s * (2 * E_PITCH / 16), dj + s * 128, s);
          else wgmma_ss_n64<HN, HN>(ya[i], du + ((s & 1) * 2 * UT_PH + ((s - 2) >> 1) * 16) / 16, dt + 32 * (s - 2), 1);
        }
      };
      auto xstore = [&](int i) {
        pin(ya[i]);
        if (w < 3) sts128(xbuf[i & 1], pack_bf16(ya[i][7], ya[i][6]), pack_bf16(ya[i][15], ya[i][14]), pack_bf16(ya[i][23], ya[i][22]), pack_bf16(ya[i][31], ya[i][30]));
      };
      auto xload = [&](int i, uint32_t (&x)[4]) {
        x[0] = x[1] = x[2] = x[3] = 0u;
        if (w > 0) lds128(x, xbuf[i & 1] - 512);
      };
      auto ystore = [&](int i, const uint32_t (&x)[4]) {
        const float (&y)[32] = ya[i];
        if (i > 1) mbar_wait(BAR(B_YFREE + i - 2), 0);
        const uint32_t a = yb + (i & 1) * 4096 + (m0 >> 1) * 128 + 12 - 4 * t;
#pragma unroll
        for (int c = 0; c < 4; c++) {
          sts32(a + 512 + ((((g & 1) * 4 + 3 - c) ^ ((g >> 1) + 4)) << 4), pack_bf16(y[8 * c + 3] + y[8 * c + 5], y[8 * c + 2] + y[8 * c + 4]));
          sts32(a + ((((g & 1) * 4 + 3 - c) ^ (g >> 1)) << 4), pack_bf16(y[8 * c + 1] + bf_lo(x[c]), y[8 * c] + bf_hi(x[c])));
        }
      };
      uint32_t xa[4], xb[4];
      PROF_T(10);
#pragma unroll
      for (int i = 0; i < 4; i++) {
        wgmma_fence();
        mma(i, 0, 6);
        wgmma_commit();
        if (i > 0) {
          wgmma_wait<1>();
          bar_sync(NBW, 128);
          if (t128 == 0) mbar_arrive(BAR(B_SFREE + i - 1));
          PROF_T(10 + i);
          if (i > 1) xload(i - 2, xa);
          xstore(i - 1);
        }
        mma(i, 6, 11);
        if (i > 1) ystore(i - 2, xa);
        mma(i, 11, 16);
        if (i > 1) { fence_async_smem(); bar_arrive(NB_MSG_Y + i - 2, 288); }
        mma(i, 16, 20);
        wgmma_commit();
      }
      wgmma_wait<0>();
      if (lane == 0) mbar_arrive(BAR(B_UTFREE));
      PROF_T(14);
      xstore(3);
      bar_sync(NBW, 128);
      xload(2, xa); xload(3, xb);
      ystore(2, xa); ystore(3, xb);
      fence_async_smem();
      bar_arrive(NB_MSG_Y + 2, 288);
      bar_arrive(NB_MSG_Y + 3, 288);
      PROF_T(15);
    }
    PROF_T(16); PROF_G(26);
    float bacc[64];
    uint32_t ga[8][4], o0, o1;
    {
      int n = 0;
      auto ostage = [&](int i) {
        mbar_wait(BAR(B_FULL + (i & 7)), (i >> 3) & 1);
        const uint32_t db = dB + out_slot(n) * (SLOT >> 4);
        n = n == 10 ? 0 : n + 1;
        const uint32_t da = dA + (i < 2 ? 11 + i : out_slot(n)) * (SLOT >> 4);
        if (i >= 2) n = n == 10 ? 0 : n + 1;
        wgmma_fence();
#pragma unroll
        for (int k = 0; k < 4; k++) wgmma_ss_n128_tb<H128, H128>(bacc, da + 2 * k, db + 128 * k, (i | k) != 0);
        wgmma_commit();
      };
#pragma unroll 1
      for (int i = 0; i < 15; i++) {
        ostage(i);
        wgmma_wait<1>();
        if (i > 0 && lane == 0) mbar_arrive(BAR(B_EMPTY + ((i - 1) & 7)));
      }
      ostage(15);
      mbar_wait(BAR(B_AT), 0);
      uint32_t g0, g1;
      lds64(g0, o0, sb + OFF_GATE + (64 * wg + 16 * w + g) * 8);
      lds64(g1, o1, sb + OFF_GATE + (64 * wg + 16 * w + g + 8) * 8);
      const int chr = (lane & 7) + (lane >> 4) * 8, lch = 2 * w + ((lane >> 3) & 1);
      const uint32_t aa = sb + OFF_IO + wg * SLOT + chr * 128 + ((lch ^ (chr & 7)) << 4);
#pragma unroll
      for (int c = 0; c < 8; c++) ldsm4t(ga[c], aa + c * 2048);
#pragma unroll
      for (int c = 0; c < 8; c++)
#pragma unroll
        for (int i = 0; i < 4; i++) ga[c][i] = hmul2(ga[c][i], (i & 1) ? g1 : g0);
      mbar_wait(BAR(B_EMPTY + (43 & 7)), (43 >> 3) & 1);
    }
    PROF_T(17);
    wgmma_wait<0>();
    pin(bacc);
    PROF_T(18); PROF_G(27);
#pragma unroll
    for (int c = 0; c < 8; c++) {
      uint32_t o[4];
#pragma unroll
      for (int i = 0; i < 4; i++) o[i] = hfma2(pack_bf16(bacc[8 * c + 2 * i], bacc[8 * c + 2 * i + 1]), (i & 1) ? o1 : o0, ga[c][i]);
      stsm4(sb + (9 + (c >> 2)) * SLOT + srow * 128 + (((2 * (c & 3) + schk) ^ (srow & 7)) << 4), o[0], o[1], o[2], o[3]);
    }
    fence_async_smem();
    __syncwarp();
    if (lane == 0) {
      tma_store_2d(&tm_out, 128 * hg, 128 * rb + 16 * warp, sb + 9 * SLOT + warp * 2048);
      tma_store_2d(&tm_out, 128 * hg + 64, 128 * rb + 16 * warp, sb + 10 * SLOT + warp * 2048);
      bulk_commit();
      bulk_wait_read();
    }
    PROF_T(19); PROF_G(28);
    PROF_DUMP(32);
  }
}

typedef CUresult (*EncodeFn)(CUtensorMap*, CUtensorMapDataType, cuuint32_t, void*, const cuuint64_t*, const cuuint64_t*, const cuuint32_t*, const cuuint32_t*,
                             CUtensorMapInterleave, CUtensorMapSwizzle, CUtensorMapL2promotion, CUtensorMapFloatOOBfill);

CUtensorMap make_map(EncodeFn enc, const void* ptr, uint64_t inner, uint64_t outer, uint32_t bi, uint32_t bo, CUtensorMapSwizzle swz, CUtensorMapL2promotion prom) {
  CUtensorMap tm;
  cuuint64_t dims[2] = {inner, outer}, strides[1] = {inner * 2};
  cuuint32_t box[2] = {bi, bo}, es[2] = {1, 1};
  enc(&tm, CU_TENSOR_MAP_DATA_TYPE_BFLOAT16, 2, const_cast<void*>(ptr), dims, strides, box, es, CU_TENSOR_MAP_INTERLEAVE_NONE, swz, prom, CU_TENSOR_MAP_FLOAT_OOB_FILL_NONE);
  return tm;
}

}

extern "C" void kernel_launch(void* const* d_in, const int* in_sizes, int n_in, void* d_out, int out_size) {
  (void)in_sizes; (void)n_in; (void)out_size;
  static EncodeFn enc = nullptr;
  static void *p_o = nullptr, *p_aT = nullptr;
  if (!enc) {
    void* fn = nullptr;
    cudaDriverEntryPointQueryResult st;
    cudaGetDriverEntryPoint("cuTensorMapEncodeTiled", &fn, cudaEnableDefault, &st);
    enc = (EncodeFn)fn;
    cudaGetSymbolAddress(&p_o, g_o);
    cudaGetSymbolAddress(&p_aT, g_aT);
    cudaFuncSetAttribute(fused_kernel, cudaFuncAttributeMaxDynamicSharedMemorySize, SMEM_BYTES);
  }
  typedef const __nv_bfloat16* bp;
  Params P;
  P.x = (bp)d_in[0]; P.a_re = (bp)d_in[1]; P.a_im = (bp)d_in[2]; P.b_re = (bp)d_in[3]; P.b_im = (bp)d_in[4]; P.c_re = (bp)d_in[5]; P.c_im = (bp)d_in[6];
  P.log_dt = (bp)d_in[7]; P.dskip = (bp)d_in[8]; P.wqkv = (bp)d_in[10]; P.wo = (bp)d_in[12]; P.gate_w = (bp)d_in[13];
  const CUtensorMapL2promotion L256 = CU_TENSOR_MAP_L2_PROMOTION_L2_256B, L128 = CU_TENSOR_MAP_L2_PROMOTION_L2_128B, LN = CU_TENSOR_MAP_L2_PROMOTION_NONE;
  const CUtensorMap tm_x = make_map(enc, P.x, 1024, 2048, 64, 128, CU_TENSOR_MAP_SWIZZLE_128B, L256);
  const CUtensorMap tm_w = make_map(enc, P.wqkv, 3072, 1024, 64, 64, CU_TENSOR_MAP_SWIZZLE_128B, L256);
  const CUtensorMap tm_wo = make_map(enc, P.wo, 1024, 1024, 64, 64, CU_TENSOR_MAP_SWIZZLE_128B, L256);
  const CUtensorMap tm_wphi = make_map(enc, d_in[11], 32, 1024, 32, 128, CU_TENSOR_MAP_SWIZZLE_64B, L128);
  const CUtensorMap tm_u = make_map(enc, P.x, 1024, 2048, 8, 256, CU_TENSOR_MAP_SWIZZLE_NONE, LN);
  const CUtensorMap tm_o = make_map(enc, p_o, 1024, 2048, 64, 128, CU_TENSOR_MAP_SWIZZLE_128B, L256);
  const CUtensorMap tm_aT = make_map(enc, p_aT, 2048, 1024, 64, 128, CU_TENSOR_MAP_SWIZZLE_128B, L128);
  const CUtensorMap tm_y = make_map(enc, p_aT, 64, 32768, 64, 32, CU_TENSOR_MAP_SWIZZLE_128B, L128);
  const CUtensorMap tm_out = make_map(enc, d_out, 1024, 2048, 64, 16, CU_TENSOR_MAP_SWIZZLE_128B, L128);
  fused_kernel<<<128, kThreads, SMEM_BYTES>>>(P, tm_x, tm_w, tm_wo, tm_wphi, tm_u, tm_o, tm_aT, tm_y, tm_out);
}
```
